```python
import torch

def _softmax(x, axis=-1):
    return torch.softmax(x, dim=axis)
def _gelu(x):
    return torch.nn.functional.gelu(x, approximate="tanh")
def _silu(x):
    return torch.nn.functional.silu(x)
def _sigmoid(x):
    return torch.sigmoid(x)
def _layernorm(x, axis=-1, eps=1e-5):
    m = x.mean(dim=axis, keepdim=True)
    v = x.var(dim=axis, keepdim=True, unbiased=False)
    return (x - m) / torch.sqrt(v + eps)
def _scatter_add(tgt, idx, src, axis=0):
    return tgt.clone().index_add_(axis, idx, src)
def _segment_sum(src, seg, n):
    out = torch.zeros((n,) + src.shape[1:], dtype=src.dtype)
    return out.index_add_(0, seg, src)
def _pad(x, pw):
    flat = tuple(v for pair in reversed(pw) for v in pair)
    return torch.nn.functional.pad(x, flat)

kernel_name = 'standalone__mha_softmax__near_ridge'

def setup_inputs():

    _w = (lambda a: (lambda t: t.to(torch.bfloat16) if t.is_floating_point() else t)(torch.as_tensor(a)))
    B, H, Sq, Sk, D = 16, 16, 368, 512, 256
    return {
        "q": _w((lambda *s: torch.randn(*s, dtype=torch.bfloat16) * 0.8)(B, H, Sq, D)),
        "k": _w((lambda *s: torch.randn(*s, dtype=torch.bfloat16) * 0.8)(B, H, Sk, D)),
        "v": _w((lambda *s: torch.randn(*s, dtype=torch.bfloat16) * 0.05)(B, H, Sk, D)),
    }

def reference(q, k, v):
    scale = q.shape[-1] ** -0.5
    scores = torch.einsum("bhqd,bhkd->bhqk", q, k) * scale
    p = _softmax(scores, axis=-1)
    return torch.einsum("bhqk,bhkd->bhqd", p, v)
```

```cpp
#include <cuda_runtime.h>
#include <cuda_bf16.h>
#include <cuda.h>
#include <stdint.h>
#include <type_traits>

namespace {

constexpr int kBH = 256;
constexpr int kSq = 368;
constexpr int kSk = 512;
constexpr int kQTiles = 3;
constexpr int kNumTiles = kBH * kQTiles;
constexpr int kChunkBytes = 16384;
constexpr int kSmemQ = 0;
constexpr int kSmemK = 98304;
constexpr int kSmemV = 163840;
constexpr int kSmemBar = 229376;
constexpr int kSmemTotal = kSmemBar + 512 + 1024;
constexpr int kThreads = 384;
constexpr float kBig = 65536.0f;

constexpr int kStagger = 100;
constexpr int kEarlyPfClusters = 24;
constexpr int kMixedPolicyTiles = 12;
constexpr uint32_t kTickStore = 0x432111, kTickLoadQ = 0x554321;
static_assert((kTickLoadQ & 0x7) >= 1 && ((kTickLoadQ >> 8) & 0x7) >= 1 && ((kTickLoadQ >> 16) & 0x7) >= 1, "");
static_assert(((kTickLoadQ >> 4) & 0x7) >= 2 && ((kTickLoadQ >> 12) & 0x7) >= 2 && ((kTickLoadQ >> 20) & 0x7) >= 2, "");
constexpr int kPauseTile = 10, kPauseSlack = 45;

__device__ __forceinline__ uint32_t smem_u32(const void* p) { return (uint32_t)__cvta_generic_to_shared(p); }

__device__ __forceinline__ void mbar_init(uint32_t bar, uint32_t count) {
    asm volatile("mbarrier.init.shared::cta.b64 [%0], %1;" ::"r"(bar), "r"(count) : "memory");
}
__device__ __forceinline__ void mbar_expect_tx(uint32_t bar, uint32_t bytes) {
    asm volatile("mbarrier.arrive.expect_tx.shared::cta.b64 _, [%0], %1;" ::"r"(bar), "r"(bytes) : "memory");
}
__device__ __forceinline__ void mbar_expect_tx_cluster(uint32_t bar_cluster_addr, uint32_t bytes) {
    asm volatile("mbarrier.arrive.expect_tx.shared::cluster.b64 _, [%0], %1;" ::"r"(bar_cluster_addr), "r"(bytes) : "memory");
}
__device__ __forceinline__ void mbar_arrive(uint32_t bar) {
    asm volatile("mbarrier.arrive.shared::cta.b64 _, [%0];" ::"r"(bar) : "memory");
}
__device__ __forceinline__ void mbar_arrive_cluster(uint32_t bar_cluster_addr) {
    asm volatile("mbarrier.arrive.shared::cluster.b64 _, [%0];" ::"r"(bar_cluster_addr) : "memory");
}
__device__ __forceinline__ void mbar_wait(uint32_t bar, uint32_t parity) {
    asm volatile(
        "{\n.reg .pred p;\n.reg .u32 n;\n"
        "mov.u32 n, 0;\n"
        "LAB_WAIT:\n"
        "mbarrier.try_wait.parity.shared::cta.b64 p, [%0], %1;\n"
        "@p bra LAB_DONE;\n"
        "add.u32 n, n, 1;\n"
        "setp.lt.u32 p, n, 4194304;\n"
        "@p bra LAB_WAIT;\n"
        "trap;\n"
        "LAB_DONE:\n}\n"
        ::"r"(bar), "r"(parity) : "memory");
}
__device__ __forceinline__ void mbar_wait2(uint32_t bar0, uint32_t bar1, uint32_t parity) {
    asm volatile(
        "{\n.reg .pred p, q;\n.reg .u32 n;\n"
        "mov.u32 n, 0;\n"
        "LAB_WAIT:\n"
        "mbarrier.try_wait.parity.shared::cta.b64 p, [%0], %2;\n"
        "mbarrier.try_wait.parity.shared::cta.b64 q, [%1], %2;\n"
        "and.pred p, p, q;\n"
        "@p bra LAB_DONE;\n"
        "add.u32 n, n, 1;\n"
        "setp.lt.u32 p, n, 4194304;\n"
        "@p bra LAB_WAIT;\n"
        "trap;\n"
        "LAB_DONE:\n}\n"
        ::"r"(bar0), "r"(bar1), "r"(parity) : "memory");
}
__device__ __forceinline__ bool mbar_test2(uint32_t bar0, uint32_t bar1, uint32_t parity) {
    uint32_t ok;
    asm volatile("{\n.reg .pred p, q;\n"
                 "mbarrier.test_wait.parity.shared::cta.b64 p, [%1], %3;\n"
                 "mbarrier.test_wait.parity.shared::cta.b64 q, [%2], %3;\n"
                 "and.pred p, p, q;\nselp.u32 %0, 1, 0, p;\n}\n"
                 : "=r"(ok) : "r"(bar0), "r"(bar1), "r"(parity) : "memory");
    return ok != 0;
}
__device__ __forceinline__ uint32_t mapa(uint32_t addr, uint32_t rank) {
    uint32_t r;
    asm volatile("mapa.shared::cluster.u32 %0, %1, %2;" : "=r"(r) : "r"(addr), "r"(rank));
    return r;
}
__device__ __forceinline__ long long globaltimer() { long long t; asm volatile("mov.u64 %0, %%globaltimer;" : "=l"(t)); return t; }
__device__ __forceinline__ void tma_load_4d(uint32_t dst, const CUtensorMap* map, uint32_t bar, int c0, int c1, int c2, int c3, uint64_t pol) {
    asm volatile(
        "cp.async.bulk.tensor.4d.shared::cluster.global.mbarrier::complete_tx::bytes.L2::cache_hint "
        "[%0], [%1, {%3, %4, %5, %6}], [%2], %7;"
        ::"r"(dst), "l"(map), "r"(bar), "r"(c0), "r"(c1), "r"(c2), "r"(c3), "l"(pol) : "memory");
}
__device__ __forceinline__ void tma_load_4d_mc(uint32_t dst, const CUtensorMap* map, uint32_t bar, int c0, int c1, int c2, int c3, uint16_t mask, uint64_t pol) {
    asm volatile(
        "cp.async.bulk.tensor.4d.shared::cluster.global.mbarrier::complete_tx::bytes.multicast::cluster.L2::cache_hint "
        "[%0], [%1, {%3, %4, %5, %6}], [%2], %7, %8;"
        ::"r"(dst), "l"(map), "r"(bar), "r"(c0), "r"(c1), "r"(c2), "r"(c3), "h"(mask), "l"(pol) : "memory");
}
__device__ __forceinline__ void tma_prefetch_4d(const CUtensorMap* map, int c0, int c1, int c2, int c3) {
    asm volatile("cp.async.bulk.prefetch.tensor.4d.L2.global.tile [%0, {%1, %2, %3, %4}];"
                 ::"l"(map), "r"(c0), "r"(c1), "r"(c2), "r"(c3) : "memory");
}
__device__ __forceinline__ void tma_store_4d(const CUtensorMap* map, uint32_t src, int c0, int c1, int c2, int c3) {
    asm volatile(
        "cp.async.bulk.tensor.4d.global.shared::cta.bulk_group [%0, {%2, %3, %4, %5}], [%1];"
        ::"l"(map), "r"(src), "r"(c0), "r"(c1), "r"(c2), "r"(c3) : "memory");
    asm volatile("cp.async.bulk.commit_group;" ::: "memory");
}
__device__ __forceinline__ void tma_store_wait_read() { asm volatile("cp.async.bulk.wait_group.read 0;" ::: "memory"); }
__device__ __forceinline__ void prefetch_tmap(const CUtensorMap* map) { asm volatile("prefetch.tensormap [%0];" ::"l"(map) : "memory"); }
__device__ __forceinline__ void stmatrix_x4(uint32_t addr, uint32_t r0, uint32_t r1, uint32_t r2, uint32_t r3) {
    asm volatile("stmatrix.sync.aligned.m8n8.x4.shared.b16 [%0], {%1, %2, %3, %4};"
                 ::"r"(addr), "r"(r0), "r"(r1), "r"(r2), "r"(r3) : "memory");
}
__device__ __forceinline__ void wgmma_fence() { asm volatile("wgmma.fence.sync.aligned;" ::: "memory"); }
__device__ __forceinline__ void wgmma_commit() { asm volatile("wgmma.commit_group.sync.aligned;" ::: "memory"); }
template <int N> __device__ __forceinline__ void wgmma_wait() { asm volatile("wgmma.wait_group.sync.aligned %0;" ::"n"(N) : "memory"); }
__device__ __forceinline__ void bar_sync(int id, int n) { asm volatile("bar.sync %0, %1;" ::"r"(id), "r"(n) : "memory"); }
__device__ __forceinline__ void bar_arrive(int id, int n) { asm volatile("bar.arrive %0, %1;" ::"r"(id), "r"(n) : "memory"); }
__device__ __forceinline__ bool wg_any(int id, bool pred) {
    uint32_t r;
    asm volatile("{\n.reg .pred p, q;\nsetp.ne.u32 p, %1, 0;\nbar.red.or.pred q, %2, 128, p;\nselp.u32 %0, 1, 0, q;\n}\n"
                 : "=r"(r) : "r"((uint32_t)pred), "r"(id) : "memory");
    return r != 0;
}
__device__ __forceinline__ float ex2(float x) { float y; asm("ex2.approx.ftz.f32 %0, %1;" : "=f"(y) : "f"(x)); return y; }
__device__ __forceinline__ uint32_t pack_bf16(float lo, float hi) {
    uint32_t r; asm("cvt.rn.bf16x2.f32 %0, %1, %2;" : "=r"(r) : "f"(hi), "f"(lo)); return r;
}
template <int N> __device__ __forceinline__ void fence_regs(float (&d)[N]) {
#pragma unroll
    for (int i = 0; i < N; i++) asm volatile("" : "+f"(d[i])::"memory");
}
__device__ __forceinline__ uint64_t make_desc(uint32_t addr, uint32_t lbo_bytes, uint32_t sbo_bytes) {
    return (uint64_t)((addr & 0x3FFFF) >> 4) | ((uint64_t)(lbo_bytes >> 4) << 16) | ((uint64_t)(sbo_bytes >> 4) << 32) | (1ull << 62);
}
template <int N> using IC = std::integral_constant<int, N>;

__device__ __forceinline__ void wgmma_ss_m64n128k16_zero(float (&d)[64], uint64_t da, uint64_t db) {
    asm volatile(
        "wgmma.mma_async.sync.aligned.m64n128k16.f32.bf16.bf16 "
        "{%0, %1, %2, %3, %4, %5, %6, %7, %8, %9, %10, %11, %12, %13, %14, %15, %16, %17, %18, %19, %20, %21, %22, %23, %24, %25, %26, %27,"
        " %28, %29, %30, %31, %32, %33, %34, %35, %36, %37, %38, %39, %40, %41, %42, %43, %44, %45, %46, %47, %48, %49, %50, %51, %52, %53,"
        " %54, %55, %56, %57, %58, %59, %60, %61, %62, %63}, %64, %65, 0, 1, 1, 0, 0;\n"
        : "=f"(d[0]), "=f"(d[1]), "=f"(d[2]), "=f"(d[3]), "=f"(d[4]), "=f"(d[5]), "=f"(d[6]), "=f"(d[7]), "=f"(d[8]), "=f"(d[9]),
          "=f"(d[10]), "=f"(d[11]), "=f"(d[12]), "=f"(d[13]), "=f"(d[14]), "=f"(d[15]), "=f"(d[16]), "=f"(d[17]), "=f"(d[18]), "=f"(d[19]),
          "=f"(d[20]), "=f"(d[21]), "=f"(d[22]), "=f"(d[23]), "=f"(d[24]), "=f"(d[25]), "=f"(d[26]), "=f"(d[27]), "=f"(d[28]), "=f"(d[29]),
          "=f"(d[30]), "=f"(d[31]), "=f"(d[32]), "=f"(d[33]), "=f"(d[34]), "=f"(d[35]), "=f"(d[36]), "=f"(d[37]), "=f"(d[38]), "=f"(d[39]),
          "=f"(d[40]), "=f"(d[41]), "=f"(d[42]), "=f"(d[43]), "=f"(d[44]), "=f"(d[45]), "=f"(d[46]), "=f"(d[47]), "=f"(d[48]), "=f"(d[49]),
          "=f"(d[50]), "=f"(d[51]), "=f"(d[52]), "=f"(d[53]), "=f"(d[54]), "=f"(d[55]), "=f"(d[56]), "=f"(d[57]), "=f"(d[58]), "=f"(d[59]),
          "=f"(d[60]), "=f"(d[61]), "=f"(d[62]), "=f"(d[63])
        : "l"(da), "l"(db));
}

__device__ __forceinline__ void wgmma_ss_m64n128k16(float (&d)[64], uint64_t da, uint64_t db) {
    asm volatile(
        "wgmma.mma_async.sync.aligned.m64n128k16.f32.bf16.bf16 "
        "{%0, %1, %2, %3, %4, %5, %6, %7, %8, %9, %10, %11, %12, %13, %14, %15, %16, %17, %18, %19, %20, %21, %22, %23, %24, %25, %26, %27,"
        " %28, %29, %30, %31, %32, %33, %34, %35, %36, %37, %38, %39, %40, %41, %42, %43, %44, %45, %46, %47, %48, %49, %50, %51, %52, %53,"
        " %54, %55, %56, %57, %58, %59, %60, %61, %62, %63}, %64, %65, 1, 1, 1, 0, 0;\n"
        : "+f"(d[0]), "+f"(d[1]), "+f"(d[2]), "+f"(d[3]), "+f"(d[4]), "+f"(d[5]), "+f"(d[6]), "+f"(d[7]), "+f"(d[8]), "+f"(d[9]),
          "+f"(d[10]), "+f"(d[11]), "+f"(d[12]), "+f"(d[13]), "+f"(d[14]), "+f"(d[15]), "+f"(d[16]), "+f"(d[17]), "+f"(d[18]), "+f"(d[19]),
          "+f"(d[20]), "+f"(d[21]), "+f"(d[22]), "+f"(d[23]), "+f"(d[24]), "+f"(d[25]), "+f"(d[26]), "+f"(d[27]), "+f"(d[28]), "+f"(d[29]),
          "+f"(d[30]), "+f"(d[31]), "+f"(d[32]), "+f"(d[33]), "+f"(d[34]), "+f"(d[35]), "+f"(d[36]), "+f"(d[37]), "+f"(d[38]), "+f"(d[39]),
          "+f"(d[40]), "+f"(d[41]), "+f"(d[42]), "+f"(d[43]), "+f"(d[44]), "+f"(d[45]), "+f"(d[46]), "+f"(d[47]), "+f"(d[48]), "+f"(d[49]),
          "+f"(d[50]), "+f"(d[51]), "+f"(d[52]), "+f"(d[53]), "+f"(d[54]), "+f"(d[55]), "+f"(d[56]), "+f"(d[57]), "+f"(d[58]), "+f"(d[59]),
          "+f"(d[60]), "+f"(d[61]), "+f"(d[62]), "+f"(d[63])
        : "l"(da), "l"(db));
}

__device__ __forceinline__ void wgmma_rs_m64n256k16_tb(float (&d)[128], uint32_t a0, uint32_t a1, uint32_t a2, uint32_t a3, uint64_t db, int
          scale_d) {
    asm volatile(
        "{\n.reg .pred p;\nsetp.ne.b32 p, %133, 0;\n"
        "wgmma.mma_async.sync.aligned.m64n256k16.f32.bf16.bf16 "
        "{%0, %1, %2, %3, %4, %5, %6, %7, %8, %9, %10, %11, %12, %13, %14, %15, %16, %17, %18, %19, %20, %21, %22, %23, %24, %25, %26, %27,"
        " %28, %29, %30, %31, %32, %33, %34, %35, %36, %37, %38, %39, %40, %41, %42, %43, %44, %45, %46, %47, %48, %49, %50, %51, %52, %53,"
        " %54, %55, %56, %57, %58, %59, %60, %61, %62, %63, %64, %65, %66, %67, %68, %69, %70, %71, %72, %73, %74, %75, %76, %77, %78, %79,"
        " %80, %81, %82, %83, %84, %85, %86, %87, %88, %89, %90, %91, %92, %93, %94, %95, %96, %97, %98, %99, %100, %101, %102, %103, %104,"
        " %105, %106, %107, %108, %109, %110, %111, %112, %113, %114, %115, %116, %117, %118, %119, %120, %121, %122, %123, %124, %125, "
        "%126, %127}, {%128, %129, %130, %131}, %132, p, 1, 1, 1;\n}\n"
        : "+f"(d[0]), "+f"(d[1]), "+f"(d[2]), "+f"(d[3]), "+f"(d[4]), "+f"(d[5]), "+f"(d[6]), "+f"(d[7]), "+f"(d[8]), "+f"(d[9]),
          "+f"(d[10]), "+f"(d[11]), "+f"(d[12]), "+f"(d[13]), "+f"(d[14]), "+f"(d[15]), "+f"(d[16]), "+f"(d[17]), "+f"(d[18]), "+f"(d[19]),
          "+f"(d[20]), "+f"(d[21]), "+f"(d[22]), "+f"(d[23]), "+f"(d[24]), "+f"(d[25]), "+f"(d[26]), "+f"(d[27]), "+f"(d[28]), "+f"(d[29]),
          "+f"(d[30]), "+f"(d[31]), "+f"(d[32]), "+f"(d[33]), "+f"(d[34]), "+f"(d[35]), "+f"(d[36]), "+f"(d[37]), "+f"(d[38]), "+f"(d[39]),
          "+f"(d[40]), "+f"(d[41]), "+f"(d[42]), "+f"(d[43]), "+f"(d[44]), "+f"(d[45]), "+f"(d[46]), "+f"(d[47]), "+f"(d[48]), "+f"(d[49]),
          "+f"(d[50]), "+f"(d[51]), "+f"(d[52]), "+f"(d[53]), "+f"(d[54]), "+f"(d[55]), "+f"(d[56]), "+f"(d[57]), "+f"(d[58]), "+f"(d[59]),
          "+f"(d[60]), "+f"(d[61]), "+f"(d[62]), "+f"(d[63]), "+f"(d[64]), "+f"(d[65]), "+f"(d[66]), "+f"(d[67]), "+f"(d[68]), "+f"(d[69]),
          "+f"(d[70]), "+f"(d[71]), "+f"(d[72]), "+f"(d[73]), "+f"(d[74]), "+f"(d[75]), "+f"(d[76]), "+f"(d[77]), "+f"(d[78]), "+f"(d[79]),
          "+f"(d[80]), "+f"(d[81]), "+f"(d[82]), "+f"(d[83]), "+f"(d[84]), "+f"(d[85]), "+f"(d[86]), "+f"(d[87]), "+f"(d[88]), "+f"(d[89]),
          "+f"(d[90]), "+f"(d[91]), "+f"(d[92]), "+f"(d[93]), "+f"(d[94]), "+f"(d[95]), "+f"(d[96]), "+f"(d[97]), "+f"(d[98]), "+f"(d[99]),
          "+f"(d[100]), "+f"(d[101]), "+f"(d[102]), "+f"(d[103]), "+f"(d[104]), "+f"(d[105]), "+f"(d[106]), "+f"(d[107]), "+f"(d[108]),
          "+f"(d[109]), "+f"(d[110]), "+f"(d[111]), "+f"(d[112]), "+f"(d[113]), "+f"(d[114]), "+f"(d[115]), "+f"(d[116]), "+f"(d[117]),
          "+f"(d[118]), "+f"(d[119]), "+f"(d[120]), "+f"(d[121]), "+f"(d[122]), "+f"(d[123]), "+f"(d[124]), "+f"(d[125]), "+f"(d[126]),
          "+f"(d[127])
        : "r"(a0), "r"(a1), "r"(a2), "r"(a3), "l"(db), "r"(scale_d));
}


template <int CL>
__global__ void __launch_bounds__(kThreads, 1)
mha_fwd_kernel(const __grid_constant__ CUtensorMap map_q, const __grid_constant__ CUtensorMap map_k,
               const __grid_constant__ CUtensorMap map_v, const __grid_constant__ CUtensorMap map_o,
               const int tile_begin, const int tile_end, const int passes_total) {
    extern __shared__ uint8_t smem_raw[];
    uint32_t smem_base = (smem_u32(smem_raw) + 1023u) & ~1023u;
    asm volatile("mov.u32 %0, %0;" : "+r"(smem_base));
    const uint32_t sQ = smem_base + kSmemQ;
    const uint32_t sK = smem_base + kSmemK;
    const uint32_t sV = smem_base + kSmemV;
    const uint32_t bar_full = smem_base + kSmemBar;
    const uint32_t bar_empty = bar_full + 64;
    const uint32_t bar_qfull = bar_empty + 64;
    const uint32_t bar_qempty = bar_qfull + 32;
    const uint32_t bar_ofull = bar_qempty + 16;
    const uint32_t bar_oempty = bar_ofull + 16;
    const uint32_t bar_tick = bar_oempty + 16;

    const int nctas = gridDim.x;
    const int tile0 = tile_begin + blockIdx.x;
    const int npass = (tile_end - tile0 + nctas - 1) / nctas;
    const int warp = __shfl_sync(0xffffffffu, threadIdx.x >> 5, 0);
    const int lane = threadIdx.x & 31;
    const int bh_step = nctas / kQTiles;
    const int bh0 = tile0 / kQTiles, qt = tile0 - bh0 * kQTiles;

    if (warp == 10) {
        if (lane == 0) {
            for (int i = 0; i < 8; i++) {
                mbar_init(bar_full + 8 * i, 1);
                mbar_init(bar_empty + 8 * i, 8 * CL);
                mbar_init(bar_tick + 8 * i, 1);
            }
            for (int i = 0; i < 2; i++) {
                mbar_init(bar_qfull + 16 * i, 1);
                mbar_init(bar_qfull + 16 * i + 8, 1);
                mbar_init(bar_qempty + 8 * i, 4);
                mbar_init(bar_ofull + 8 * i, 4);
                mbar_init(bar_oempty + 8 * i, 1);
            }
            asm volatile("fence.mbarrier_init.release.cluster;" ::: "memory");
        }
        __syncwarp();
    } else if (warp == 8) {
        if (lane == 0) {
            prefetch_tmap(&map_k);
            if (CL == 1 || (int)blockIdx.x < 3 * kEarlyPfClusters)
                for (int cc = qt; cc < 4; cc += 3) tma_prefetch_4d(&map_k, 0, 0, cc, bh0);
        }
        __syncwarp();
    } else if (warp == 9) {
        if (lane == 0) prefetch_tmap(&map_v);
        __syncwarp();
    } else if (warp == 11) {
        if (lane == 0) { prefetch_tmap(&map_q); prefetch_tmap(&map_o); }
        __syncwarp();
    }
    if (CL > 1) {
        asm volatile("barrier.cluster.arrive.relaxed.aligned;" ::: "memory");
        asm volatile("barrier.cluster.wait.acquire.aligned;" ::: "memory");
        asm volatile("griddepcontrol.launch_dependents;");
    } else {
        __syncthreads();
    }

    if (warp >= 8) {
        asm volatile("setmaxnreg.dec.sync.aligned.u32 24;");
        if (CL > 1) {
            const long long t0 = clock64(), d = (long long)(blockIdx.x / 3) * kStagger;
            while (clock64() - t0 < d) {}
        }
        if (warp < 10) {
            if (lane == 0) {
                uint64_t pol_kv, pol_early;
                if (CL > 1) {
                    asm volatile("createpolicy.fractional.L2::evict_first.b64 %0, 1.0;" : "=l"(pol_kv));
                    asm volatile("createpolicy.fractional.L2::evict_first.b64 %0, 0.5;" : "=l"(pol_early));
                } else {
                    asm volatile("createpolicy.fractional.L2::evict_normal.b64 %0, 1.0;" : "=l"(pol_kv));
                }
                const int isv = warp - 8;
                const CUtensorMap* map = isv ? &map_v : &map_k;
                const int ntile = npass * 4;
                const int cfirst = (qt + 3 - isv) % 3;
                const int pf_stop = ntile - 9 + (int)(blockIdx.x / 3) * 3 / 10;
                long long tstart = 0;
                uint32_t ph = 1;
                if (isv) mbar_wait(bar_qfull, 0);
                for (int t = 0; t < ntile; t++) {
                    const int bh = bh0 + (t >> 2) * bh_step;
                    const int key0 = (t & 3) * 128;
                    if (CL == 1) {
                        if (t == 4) tstart = globaltimer();
                        if (t == kPauseTile && passes_total > npass) {
                            const long long now = globaltimer();
                            const long long until = now + (now - tstart) * 4 * ((passes_total - npass) * 100 - kPauseSlack) / (100 * (kPauseTile - 4));
                            while (globaltimer() < until) __nanosleep(200);
                        }
                    }
#pragma unroll 1
                    for (int cc = (CL == 1) ? 0 : cfirst; cc < 4; cc += (CL == 1) ? 1 : 3) {
                        const int c = isv * 4 + cc;
                        const uint32_t fb = bar_full + 8 * c;
                        const int c1 = isv ? key0 + cc * 32 : key0;
                        const int c2 = isv ? 0 : cc;
                        mbar_wait(bar_empty + 8 * c, ph);
                        if (CL > 1) {
                            tma_load_4d_mc(sK + c * kChunkBytes, map, fb, 0, c1, c2, bh, (uint16_t)7, t < kMixedPolicyTiles ? pol_early : pol_kv);
#pragma unroll
                            for (int r = 0; r < CL; r++) mbar_expect_tx_cluster(mapa(fb, r), kChunkBytes);
                            if (t > 0 && t < pf_stop && t + 1 < ntile) {
                                const int k2 = ((t + 1) & 3) * 128;
                                tma_prefetch_4d(map, 0, isv ? k2 + cc * 32 : k2, c2, bh0 + ((t + 1) >> 2) * bh_step);
                            }
                        } else {
                            mbar_expect_tx(fb, kChunkBytes);
                            tma_load_4d(sK + c * kChunkBytes, map, fb, 0, c1, c2, bh, pol_kv);
                        }
                    }
                    if (CL > 1 && t == 0) {
                        mbar_wait(bar_full + 8 * (isv * 4 + cfirst), 0);
#pragma unroll 1
                        for (int cc = cfirst; cc < 4; cc += 3) tma_prefetch_4d(map, 0, isv ? 128 + cc * 32 : 128, isv ? 0 : cc, bh0);
                    }
                    ph ^= 1;
                }
            }
        } else if (lane == 0) {
            uint64_t pol_q;
            asm volatile("createpolicy.fractional.L2::evict_first.b64 %0, 1.0;" : "=l"(pol_q));
            const int w = warp - 10;
            const int row0 = qt * 128 + w * 64;
            const uint32_t units = sQ + w * 49152;
            const uint32_t qf = bar_qfull + 16 * w;
            const uint32_t tick_store = bar_tick + 8 * ((kTickStore >> (4 * (2 * qt + w))) & 7);
            const uint32_t tick_loadq = bar_tick + 8 * ((kTickLoadQ >> (4 * (2 * qt + w))) & 7);
            mbar_expect_tx(qf, 16384);
            tma_load_4d(units, &map_q, qf, 0, row0, 0, bh0, pol_q);
            mbar_expect_tx(qf + 8, 16384);
            tma_load_4d(units + 16384, &map_q, qf + 8, 0, row0, 2, bh0, pol_q);
            int ia = 0;
            for (int p = 0; p < npass; p++) {
                const int bh = bh0 + p * bh_step;
                const int ib = ia == 2 ? 0 : ia + 1, iz = ia == 0 ? 2 : ia - 1;
                const uint32_t ua = units + ia * 16384, ub = units + ib * 16384, uz = units + iz * 16384;
                if (p > 0) {
                    mbar_wait(bar_ofull + 8 * w, 1);
                    mbar_wait(tick_store, p & 1);
                    tma_store_4d(&map_o, uz, 0, row0, 2, bh - bh_step);
                    tma_store_wait_read();
                }
                if (p + 1 < npass) {
                    mbar_wait(tick_loadq, p & 1);
                    mbar_expect_tx(qf, 16384);
                    tma_load_4d(uz, &map_q, qf, 0, row0, 0, bh + bh_step, pol_q);
                    mbar_wait(bar_qempty + 8 * w, p & 1);
                    mbar_expect_tx(qf + 8, 16384);
                    tma_load_4d(ua, &map_q, qf + 8, 0, row0, 2, bh + bh_step, pol_q);
                }
                mbar_wait(bar_ofull + 8 * w, 0);
                tma_store_4d(&map_o, ub, 0, row0, 0, bh);
                if (p + 1 < npass) {
                    tma_store_wait_read();
                    mbar_arrive(bar_oempty + 8 * w);
                } else {
                    tma_store_4d(&map_o, ua, 0, row0, 2, bh);
                    tma_store_wait_read();
                }
                ia = iz;
            }
        }
    } else {
        asm volatile("setmaxnreg.inc.sync.aligned.u32 240;");
        const int wg = warp >> 2;
        const float c = 0.0625f * 1.4426950408889634f;
        const uint64_t descK = make_desc(sK, 16, 1024);
        const uint64_t descV = make_desc(sV, 4096, 1024);
        const int my_bar = 1 + wg, other_bar = 2 - wg;
        if (wg == 1) bar_arrive(1, 256);

        float o[128];
#pragma unroll
        for (int i = 0; i < 128; i++) o[i] = 0.f;
        uint32_t ph = 0;

        const int srow = (warp & 3) * 16 + (lane & 7) + ((lane >> 3) & 1) * 8;
        const uint32_t st_off = srow * 128 + (((lane >> 4) ^ (srow & 7)) << 4);
        auto stage_half = [&](auto hc, uint32_t buf) {
            constexpr int h = decltype(hc)::value;
#pragma unroll
            for (int i = 0; i < 8; i++)
                stmatrix_x4(buf + ((st_off + (i >> 2) * 8192) ^ ((i & 3) << 5)),
                            __float_as_uint(o[64 * h + 4 * i]), __float_as_uint(o[64 * h + 4 * i + 1]),
                            __float_as_uint(o[64 * h + 4 * i + 2]), __float_as_uint(o[64 * h + 4 * i + 3]));
        };
        auto publish = [&]() {
            asm volatile("fence.proxy.async.shared::cta;" ::: "memory");
            __syncwarp();
            if (lane == 0) mbar_arrive(bar_ofull + 8 * wg);
        };

        const uint32_t units = sQ + wg * 49152;
        int ia = 0;
        for (int p = 0; p < npass; p++) {
            float m0 = 0.f, m1 = 0.f, l0 = 0.f, l1 = 0.f;
            const int ib = ia == 2 ? 0 : ia + 1, iz = ia == 0 ? 2 : ia - 1;
            const uint64_t descQa = make_desc(units + ia * 16384, 16, 1024), descQb = make_desc(units + ib * 16384, 16, 1024);
            mbar_wait(bar_qfull + 16 * wg, p & 1);
#pragma unroll 1
            for (int j = 0; j < 4; j++) {
                const bool last = (j == 3) && (p == npass - 1);
                const bool rel = (lane == 0) && !last;
                auto release = [&](int s) {
                    if (rel) {
                        if (CL > 1) mbar_arrive_cluster(mapa(bar_empty + 8 * s, s % 3));
                        else mbar_arrive(bar_empty + 8 * s);
                    }
                };
                float s[64];
                mbar_wait(bar_full, ph);
                bar_sync(my_bar, 256);
#pragma unroll
                for (int ch = 0; ch < 4; ch++) {
                    if (ch > 0) mbar_wait(bar_full + 8 * ch, ph);
                    if (ch == 2 && j == 0) mbar_wait(bar_qfull + 16 * wg + 8, p & 1);
                    wgmma_fence();
#pragma unroll
                    for (int kk = 0; kk < 4; kk++) {
                        if (ch == 0 && kk == 0) wgmma_ss_m64n128k16_zero(s, descQa, descK);
                        else wgmma_ss_m64n128k16(s, (ch < 2 ? descQa : descQb) + (ch & 1) * 512 + kk * 2, descK + ch * 1024 + kk * 2);
                    }
                    wgmma_commit();
                }
                if (wg == 0) bar_arrive(other_bar, 256);
                if (threadIdx.x == 0) mbar_arrive(bar_tick + 16 * j);
                wgmma_wait<3>(); release(0);
                wgmma_wait<2>(); release(1);
                wgmma_wait<1>(); release(2);
                wgmma_wait<0>();
                fence_regs(s);
                release(3);

                uint32_t pr[32];
                float t0, t1;
                auto row_max = [&](auto hc, float& x0, float& x1) {
                    constexpr int h = decltype(hc)::value;
                    float a[2], b[2];
#pragma unroll
                    for (int q = 0; q < 2; q++) {
                        const int z = 32 * h + 16 * q;
                        a[q] = fmaxf(fmaxf(fmaxf(s[z], s[z + 1]), fmaxf(s[z + 4], s[z + 5])), fmaxf(fmaxf(s[z + 8], s[z + 9]), fmaxf(s[z + 12], s[z + 13])));
                        b[q] = fmaxf(fmaxf(fmaxf(s[z + 2], s[z + 3]), fmaxf(s[z + 6], s[z + 7])), fmaxf(fmaxf(s[z + 10], s[z + 11]), fmaxf(s[z + 14], s[z + 15])));
                    }
                    x0 = fmaxf(a[0], a[1]); x1 = fmaxf(b[0], b[1]);
                    x0 = fmaxf(x0, __shfl_xor_sync(0xffffffffu, x0, 1));
                    x1 = fmaxf(x1, __shfl_xor_sync(0xffffffffu, x1, 1));
                    x0 = fmaxf(x0, __shfl_xor_sync(0xffffffffu, x0, 2));
                    x1 = fmaxf(x1, __shfl_xor_sync(0xffffffffu, x1, 2));
                };
                auto weights = [&](auto hc) {
                    constexpr int h = decltype(hc)::value;
                    const float b0 = -m0 * c, b1 = -m1 * c;
                    t0 = 0.f; t1 = 0.f;
#pragma unroll
                    for (int i = 8 * h; i < 8 * h + 8; i++) {
                        const float e0 = ex2(fmaf(s[4 * i], c, b0)), e1 = ex2(fmaf(s[4 * i + 1], c, b0));
                        const float e2 = ex2(fmaf(s[4 * i + 2], c, b1)), e3 = ex2(fmaf(s[4 * i + 3], c, b1));
                        t0 += e0 + e1; t1 += e2 + e3;
                        pr[2 * i] = pack_bf16(e0, e1);
                        pr[2 * i + 1] = pack_bf16(e2, e3);
                    }
                };
                auto rescale = [&](auto hc) {
                    float x0, x1;
                    row_max(hc, x0, x1);
                    x0 = fmaxf(x0, m0); x1 = fmaxf(x1, m1);
                    const float a0 = ex2((m0 - x0) * c), a1 = ex2((m1 - x1) * c);
                    m0 = x0; m1 = x1;
                    l0 *= a0; l1 *= a1;
#pragma unroll
                    for (int i = 0; i < 32; i++) {
                        o[4 * i] *= a0; o[4 * i + 1] *= a0; o[4 * i + 2] *= a1; o[4 * i + 3] *= a1;
                    }
                    weights(hc);
                    fence_regs(o);
                };
                auto pv = [&](auto cc) {
                    constexpr int ch = decltype(cc)::value;
                    wgmma_fence();
#pragma unroll
                    for (int kk = 0; kk < 2; kk++) {
                        const int r = 8 * ch + 4 * kk;
                        wgmma_rs_m64n256k16_tb(o, pr[r], pr[r + 1], pr[r + 2], pr[r + 3], descV + ch * 1024 + kk * 128,
                                               (r > 0 || j > 0) ? 1 : 0);
                    }
                    wgmma_commit();
                };

                if (j == 0) row_max(IC<0>{}, m0, m1);
                const bool va = mbar_test2(bar_full + 8 * 4, bar_full + 8 * 5, ph);
                weights(IC<0>{});
                if (j == 0 && p > 0) {
                    mbar_wait(bar_oempty + 8 * wg, (p - 1) & 1);
                    stage_half(IC<1>{}, units + iz * 16384);
                }
                if (__any_sync(0xffffffffu, !(fmaxf(t0, t1) <= kBig) || !va)) {
                    if (__any_sync(0xffffffffu, !(fmaxf(t0, t1) <= kBig))) rescale(IC<0>{});
                    mbar_wait2(bar_full + 8 * 4, bar_full + 8 * 5, ph);
                }
                if (j == 3 && lane == 0) mbar_arrive(bar_qempty + 8 * wg);
                pv(IC<0>{});
                pv(IC<1>{});
                const bool vb = mbar_test2(bar_full + 8 * 6, bar_full + 8 * 7, ph);
                l0 += t0; l1 += t1;
                weights(IC<1>{});
                bool redo = false;
                if (__any_sync(0xffffffffu, !(fmaxf(t0, t1) <= kBig) || !vb)) {
                    redo = __any_sync(0xffffffffu, !(fmaxf(t0, t1) <= kBig));
                    if (redo) {
#pragma unroll
                        for (int i = 16; i < 32; i++) pr[i] = 0u;
                        t0 = 0.f; t1 = 0.f;
                    }
                    mbar_wait2(bar_full + 8 * 6, bar_full + 8 * 7, ph);
                }
                pv(IC<2>{});
                pv(IC<3>{});
                if (wg == 1 && !last) bar_arrive(other_bar, 256);
                if (threadIdx.x == 0) mbar_arrive(bar_tick + 16 * j + 8);
                if (j == 0 && p > 0) publish();
                l0 += t0; l1 += t1;
                if (wg_any(3 + wg, redo)) {
                    wgmma_wait<0>();
                    fence_regs(o);
                    if (redo) {
                        rescale(IC<1>{});
                        l0 += t0; l1 += t1;
                    } else {
#pragma unroll
                        for (int i = 16; i < 32; i++) pr[i] = 0u;
                    }
                    pv(IC<2>{});
                    pv(IC<3>{});
                    wgmma_wait<0>();
                    fence_regs(o);
                }
                if (j == 3) {
                    l0 += __shfl_xor_sync(0xffffffffu, l0, 1);
                    l1 += __shfl_xor_sync(0xffffffffu, l1, 1);
                    l0 += __shfl_xor_sync(0xffffffffu, l0, 2);
                    l1 += __shfl_xor_sync(0xffffffffu, l1, 2);
                    l0 = __frcp_rn(l0); l1 = __frcp_rn(l1);
                }
                wgmma_wait<3>(); release(4);
                wgmma_wait<2>(); release(5);
                wgmma_wait<1>(); release(6);
                wgmma_wait<0>();
                fence_regs(o);
                release(7);
                ph ^= 1;
            }
#pragma unroll
            for (int g = 0; g < 32; g++) {
                const uint32_t r0 = pack_bf16(o[4 * g] * l0, o[4 * g + 1] * l0);
                const uint32_t r1 = pack_bf16(o[4 * g + 2] * l1, o[4 * g + 3] * l1);
                const int d = (g >> 4) * 64 + (g & 15) * 2;
                o[d] = __uint_as_float(r0); o[d + 1] = __uint_as_float(r1);
            }
            stage_half(IC<0>{}, units + ib * 16384);
            if (p + 1 == npass) stage_half(IC<1>{}, units + ia * 16384);
            publish();
            ia = iz;
        }
    }
}

typedef CUresult (*EncodeTiledFn)(CUtensorMap*, CUtensorMapDataType, cuuint32_t, void*, const cuuint64_t*, const cuuint64_t*,
                                  const cuuint32_t*, const cuuint32_t*, CUtensorMapInterleave, CUtensorMapSwizzle,
                                  CUtensorMapL2promotion, CUtensorMapFloatOOBfill);

void make_map(EncodeTiledFn fn, CUtensorMap* m, const void* ptr, int rows, uint32_t box_rows, uint32_t box_chunks) {
    cuuint64_t dims[4] = {64, (cuuint64_t)rows, 4, (cuuint64_t)kBH};
    cuuint64_t strides[3] = {512, 128, (cuuint64_t)rows * 512};
    cuuint32_t box[4] = {64, box_rows, box_chunks, 1};
    cuuint32_t estr[4] = {1, 1, 1, 1};
    fn(m, CU_TENSOR_MAP_DATA_TYPE_BFLOAT16, 4, const_cast<void*>(ptr), dims, strides, box, estr,
       CU_TENSOR_MAP_INTERLEAVE_NONE, CU_TENSOR_MAP_SWIZZLE_128B, CU_TENSOR_MAP_L2_PROMOTION_NONE,
       CU_TENSOR_MAP_FLOAT_OOB_FILL_NONE);
}

}

extern "C" void kernel_launch(void* const* d_in, const int* in_sizes, int n_in, void* d_out, int out_size) {
    (void)in_sizes; (void)n_in; (void)out_size;
    static EncodeTiledFn encode = nullptr;
    static int ncl = 0, nsm = 0;
    if (!encode) {
        void* fn = nullptr;
        cudaDriverEntryPointQueryResult st;
        cudaGetDriverEntryPoint("cuTensorMapEncodeTiled", &fn, cudaEnableDefault, &st);
        encode = (EncodeTiledFn)fn;
        cudaFuncSetAttribute(mha_fwd_kernel<3>, cudaFuncAttributeMaxDynamicSharedMemorySize, kSmemTotal);
        cudaFuncSetAttribute(mha_fwd_kernel<1>, cudaFuncAttributeMaxDynamicSharedMemorySize, kSmemTotal);
        int dev = 0;
        cudaGetDevice(&dev);
        cudaDeviceGetAttribute(&nsm, cudaDevAttrMultiProcessorCount, dev);
        cudaLaunchConfig_t cfg = {};
        cfg.gridDim = dim3(3 * (nsm / 3)); cfg.blockDim = dim3(kThreads); cfg.dynamicSmemBytes = kSmemTotal;
        cudaLaunchAttribute at[1];
        at[0].id = cudaLaunchAttributeClusterDimension; at[0].val.clusterDim.x = 3; at[0].val.clusterDim.y = 1; at[0].val.clusterDim.z = 1;
        cfg.attrs = at; cfg.numAttrs = 1;
        if (cudaOccupancyMaxActiveClusters(&ncl, mha_fwd_kernel<3>, &cfg) != cudaSuccess) { ncl = 0; (void)cudaGetLastError(); }
        if (ncl > nsm / 3) ncl = nsm / 3;
        if (ncl > kBH) ncl = kBH;
    }
    CUtensorMap mq, mk, mv, mo;
    make_map(encode, &mq, d_in[0], kSq, 64, 2);
    make_map(encode, &mk, d_in[1], kSk, 128, 1);
    make_map(encode, &mv, d_in[2], kSk, 32, 4);
    make_map(encode, &mo, d_out, kSq, 64, 2);

    int triples = (nsm - 3 * ncl) / 3;
    const int per_pass = ncl + triples;
    const int passes = (kBH + per_pass - 1) / per_pass;
    const int heads_a = ncl * passes < kBH ? ncl * passes : kBH;
    if (triples > kBH - heads_a) triples = kBH - heads_a;
    if (heads_a > 0) {
        cudaLaunchConfig_t cfg = {};
        cfg.gridDim = dim3(3 * ncl); cfg.blockDim = dim3(kThreads); cfg.dynamicSmemBytes = kSmemTotal; cfg.stream = cudaStreamPerThread;
        cudaLaunchAttribute at[1];
        at[0].id = cudaLaunchAttributeClusterDimension; at[0].val.clusterDim.x = 3; at[0].val.clusterDim.y = 1; at[0].val.clusterDim.z = 1;
        cfg.attrs = at; cfg.numAttrs = 1;
        cudaLaunchKernelEx(&cfg, mha_fwd_kernel<3>, mq, mk, mv, mo, 0, heads_a * 3, passes);
    }
    if (heads_a < kBH) {
        cudaLaunchConfig_t cfg = {};
        cfg.gridDim = dim3(3 * triples); cfg.blockDim = dim3(kThreads); cfg.dynamicSmemBytes = kSmemTotal; cfg.stream = cudaStreamPerThread;
        cudaLaunchAttribute at[1];
        at[0].id = cudaLaunchAttributeProgrammaticStreamSerialization; at[0].val.programmaticStreamSerializationAllowed = 1;
        cfg.attrs = at; cfg.numAttrs = heads_a > 0 ? 1 : 0;
        cudaLaunchKernelEx(&cfg, mha_fwd_kernel<1>, mq, mk, mv, mo, heads_a * 3, kNumTiles, passes);
    }
}
```
